```python
import torch

def _softmax(x, axis=-1):
    return torch.softmax(x, dim=axis)
def _gelu(x):
    return torch.nn.functional.gelu(x, approximate="tanh")
def _silu(x):
    return torch.nn.functional.silu(x)
def _sigmoid(x):
    return torch.sigmoid(x)
def _layernorm(x, axis=-1, eps=1e-5):
    m = x.mean(dim=axis, keepdim=True)
    v = x.var(dim=axis, keepdim=True, unbiased=False)
    return (x - m) / torch.sqrt(v + eps)
def _scatter_add(tgt, idx, src, axis=0):
    return tgt.clone().index_add_(axis, idx, src)
def _segment_sum(src, seg, n):
    out = torch.zeros((n,) + src.shape[1:], dtype=src.dtype)
    return out.index_add_(0, seg, src)
def _pad(x, pw):
    flat = tuple(v for pair in reversed(pw) for v in pair)
    return torch.nn.functional.pad(x, flat)

kernel_name = 'recurrent_scan__sliding_block__glu_gated_swiglu__prompt'

def setup_inputs():

    _w = (lambda a: (lambda t: t.to(torch.bfloat16) if t.is_floating_point() else t)(torch.as_tensor(a)))
    def _A_setup():
        B, S, D = 1, 2048, 448
        return {
            "x": _w((lambda *s: torch.randn(*s, dtype=torch.bfloat16) * 0.05)(B, S, D)),
            "wqkv": _w((lambda *s: torch.randn(*s, dtype=torch.bfloat16) * 0.2)(D, 3 * D)),
            "wo": _w((lambda *s: torch.randn(*s, dtype=torch.bfloat16) * 0.2)(D, D)),
        }
    _A_in = _A_setup()

    def _B_setup():
        B, S, D, F = 1, 2048, 448, 1792
        return {
            "x": _w((lambda *s: torch.randn(*s, dtype=torch.bfloat16) * 0.05)(B, S, D)),
            "w1": _w((lambda *s: torch.randn(*s, dtype=torch.bfloat16) * 0.1)(D, F) * (2.0 / D) ** 0.5),
            "w3": _w((lambda *s: torch.randn(*s, dtype=torch.bfloat16) * 0.1)(D, F) * (2.0 / D) ** 0.5),
            "w2": _w((lambda *s: torch.randn(*s, dtype=torch.bfloat16) * 0.1)(F, D) * (2.0 / F) ** 0.5),
        }
    _B_in = _B_setup()

    return {
        "A_x": _A_in["x"],
        "A_wqkv": _A_in["wqkv"],
        "A_wo": _A_in["wo"],
        "B_x": _B_in["x"],
        "B_w1": _B_in["w1"],
        "B_w3": _B_in["w3"],
        "B_w2": _B_in["w2"],
    }

def reference(A_x, A_wqkv, A_wo, B_x, B_w1, B_w3, B_w2):
    def _A_ref(x, wqkv, wo):
        B, S, D = x.shape
        H = 16; Dh = D // H; W = 256
        qkv = (lambda x, *d: x.permute(*d))((x @ wqkv).reshape(B, S, 3, H, Dh), 2, 0, 3, 1, 4)
        q, k, v = qkv[0], qkv[1], qkv[2]
        scores = torch.einsum("bhqd,bhkd->bhqk", q, k) * (Dh ** -0.5)
        idx = torch.arange(S)
        mask = (idx[:, None] - idx[None, :] >= 0) & (idx[:, None] - idx[None, :] < W)
        scores = torch.where(mask[None, None], scores, -1e9)
        p = _softmax(scores, axis=-1)
        o = torch.einsum("bhqk,bhkd->bhqd", p, v)
        return (lambda x, *d: x.permute(*d))(o, 0, 2, 1, 3).reshape(B, S, D) @ wo

    def _B_ref(x, w1, w3, w2):
        gate = torch.einsum("bsd,df->bsf", x, w1)
        up = torch.einsum("bsd,df->bsf", x, w3)
        h = _silu(gate) * up
        out = torch.einsum("bsf,fd->bsd", h, w2)
        return out

    x = A_x
    xn = _layernorm(x, axis=-1)
    s = _A_ref(xn, A_wqkv, A_wo)
    g = _silu(_B_ref(xn, B_w1, B_w3, B_w2))
    return x + s * g
```

```cpp
#include <cuda_runtime.h>
#include <cuda_bf16.h>
#include <cuda.h>
#include <stdint.h>
#include <stdio.h>

namespace {

constexpr int SEQ = 2048, DM = 448;
constexpr int NTILE = 16;
constexpr int NJ = 8;

constexpr uint32_t SM_XN   = 0;
constexpr uint32_t SM_RING = 114688;
constexpr uint32_t RING_STAGE = 12288;
constexpr int      NSTAGE  = 6;
constexpr uint32_t SM_KV   = SM_RING + NSTAGE * RING_STAGE;
constexpr uint32_t SM_STG  = SM_KV + 32768;
constexpr uint32_t SM_BAR  = SM_STG + 8192;
constexpr uint32_t SM_TOTAL = SM_BAR + 1024 + 1024;

constexpr int B_FULL = 0, B_EMPTY = 8, B_KVFULL = 16, B_KVEMPTY = 24, B_XDEAD = 32  , B_XFULL = 40  ;
constexpr int B_XCONS = 48  , B_QKV = 55, B_OFULL = 56  , B_X = 64  , B_QKV2 = 68, B_O0 = 69, B_O1 = 70, B_LN = 71  , B_OE = 73  ;
constexpr unsigned long long BAR_COUNTS = 0x0108011004011001ull;
constexpr uint32_t SM_TAG = 640;

constexpr uint32_t PART_BYTES = 7168;

__device__ __align__(1024) uint8_t g_kv[NTILE * NJ * 32768];
__device__ __align__(1024) __nv_bfloat16 g_o[2 * SEQ * 256];
__device__ __align__(1024) uint8_t g_q[NTILE * NJ * 8192];
__device__ __align__(1024) uint8_t g_part[NTILE * NJ * NJ * 2 * PART_BYTES];
__device__ __align__(128) unsigned g_kv_flag[NTILE * NJ * 8];
__device__ __align__(128) unsigned g_o_flag[NTILE * 32];
__device__ unsigned g_epoch;
__device__ unsigned g_done;

#define DBGC 0
#define DBG(bit) ((DBGC) & (bit))
#define PROF2(k, st) do {} while (0)
#define PROF(idx) do {} while (0)
#define GP(k) do { if (t128 == 0) PROF(8 + wg * 16 + (k)); } while (0)
constexpr unsigned SPIN_LIMIT = 1u << 20;

__device__ __forceinline__ uint32_t smem_u32(const void* p) { return (uint32_t)__cvta_generic_to_shared(p); }
__device__ __forceinline__ void mbar_init(uint32_t bar, int cnt) { asm volatile("mbarrier.init.shared::cta.b64 [%0], %1;" :: "r"(bar), "r"(cnt) : "memory"); }
__device__ __forceinline__ void mbar_expect_tx(uint32_t bar, uint32_t bytes) { asm volatile("mbarrier.arrive.expect_tx.shared::cta.b64 _, [%0], %1;" :: "r"(bar), "r"(bytes) : "memory"); }
__device__ __forceinline__ void mbar_arrive(uint32_t bar) { asm volatile("mbarrier.arrive.shared::cta.b64 _, [%0];" :: "r"(bar) : "memory"); }
__device__ __forceinline__ void mbar_wait(uint32_t bar, uint32_t parity) {
  uint32_t done, it = 0;
  do {
    asm volatile("{\n.reg .pred p;\nmbarrier.try_wait.parity.shared::cta.b64 p, [%1], %2;\nselp.u32 %0, 1, 0, p;\n}\n" : "=r"(done) : "r"(bar), "r"(parity) : "memory");
  } while (!done && ++it < SPIN_LIMIT);
}
__device__ __forceinline__ void mbar_wait_sleep(uint32_t bar, uint32_t parity) {
  uint32_t done, it = 0;
  do {
    asm volatile("{\n.reg .pred p;\nmbarrier.try_wait.parity.shared::cta.b64 p, [%1], %2, %3;\nselp.u32 %0, 1, 0, p;\n}\n" : "=r"(done) : "r"(bar), "r"(parity), "r"(2000u) : "memory");
  } while (!done && ++it < (SPIN_LIMIT >> 4));
}
__device__ __forceinline__ unsigned ld_relaxed(const unsigned* p) { unsigned v; asm volatile("ld.relaxed.gpu.global.u32 %0, [%1];" : "=r"(v) : "l"(p) : "memory"); return v; }
__device__ __forceinline__ void st_relaxed(unsigned* p, unsigned v) { asm volatile("st.relaxed.gpu.global.u32 [%0], %1;" :: "l"(p), "r"(v) : "memory"); }
__device__ __forceinline__ void flag_wait(const unsigned* p, unsigned tag) {
  unsigned it = 0;
  while (ld_relaxed(p) != tag && ++it < SPIN_LIMIT) {}
}
__device__ __forceinline__ uint4 ld_b128(const void* p) {
  uint4 r;
  asm volatile("{\n.reg .b128 v;\nld.relaxed.gpu.global.b128 v, [%4];\nmov.b128 {%0, %1, %2, %3}, v;\n}\n" : "=r"(r.x), "=r"(r.y), "=r"(r.z), "=r"(r.w) : "l"(p) : "memory");
  return r;
}
__device__ __forceinline__ uint2 ld_b64(const void* p) {
  uint2 r;
  asm volatile("{\n.reg .b64 v;\nld.relaxed.gpu.global.b64 v, [%2];\nmov.b64 {%0, %1}, v;\n}\n" : "=r"(r.x), "=r"(r.y) : "l"(p) : "memory");
  return r;
}
__device__ __forceinline__ void st_b64(void* p, uint32_t a, uint32_t b) {
  asm volatile("{\n.reg .b64 v;\nmov.b64 v, {%1, %2};\nst.relaxed.gpu.global.b64 [%0], v;\n}\n" :: "l"(p), "r"(a), "r"(b) : "memory");
}
__device__ __forceinline__ void st_b128(void* p, uint32_t a, uint32_t b, uint32_t c, uint32_t d) {
  asm volatile("{\n.reg .b128 v;\nmov.b128 v, {%1, %2, %3, %4};\nst.relaxed.gpu.global.b128 [%0], v;\n}\n" :: "l"(p), "r"(a), "r"(b), "r"(c), "r"(d) : "memory");
}
__device__ __forceinline__ void arrive_pair(uint32_t bar, int lane) {
  if (lane < 2) asm volatile("{\n.reg .b32 ra;\nmapa.shared::cluster.u32 ra, %0, %1;\nmbarrier.arrive.shared::cluster.b64 _, [ra];\n}\n" :: "r"(bar), "r"(lane) : "memory");
}
__device__ __forceinline__ void fence_proxy_async_smem() { asm volatile("fence.proxy.async.shared::cta;" ::: "memory"); }

__device__ __forceinline__ void tma2d(uint32_t dst, const CUtensorMap* tm, uint32_t bar, int c0, int c1) {
  asm volatile("cp.async.bulk.tensor.2d.shared::cluster.global.mbarrier::complete_tx::bytes [%0], [%1, {%3, %4}], [%2];"
    :: "r"(dst), "l"((uint64_t)tm), "r"(bar), "r"(c0), "r"(c1) : "memory");
}
__device__ __forceinline__ void tma2d_mc(uint32_t dst, const CUtensorMap* tm, uint32_t bar, int c0, int c1) {
  asm volatile("cp.async.bulk.tensor.2d.shared::cluster.global.mbarrier::complete_tx::bytes.multicast::cluster [%0], [%1, {%3, %4}], [%2], %5;"
    :: "r"(dst), "l"((uint64_t)tm), "r"(bar), "r"(c0), "r"(c1), "h"((uint16_t)3) : "memory");
}
__device__ __forceinline__ void tma3d_mc(uint32_t dst, const CUtensorMap* tm, uint32_t bar, int c0, int c1, int c2) {
  asm volatile("cp.async.bulk.tensor.3d.shared::cluster.global.mbarrier::complete_tx::bytes.multicast::cluster [%0], [%1, {%3, %4, %5}], [%2], %6;"
    :: "r"(dst), "l"((uint64_t)tm), "r"(bar), "r"(c0), "r"(c1), "r"(c2), "h"((uint16_t)3) : "memory");
}
__device__ __forceinline__ void tma5d_mc(uint32_t dst, const CUtensorMap* tm, uint32_t bar, int c0, int c1, int c2, int c3, int c4) {
  asm volatile("cp.async.bulk.tensor.5d.shared::cluster.global.mbarrier::complete_tx::bytes.multicast::cluster [%0], [%1, {%3, %4, %5, %6, %7}], [%2], %8;"
    :: "r"(dst), "l"((uint64_t)tm), "r"(bar), "r"(c0), "r"(c1), "r"(c2), "r"(c3), "r"(c4), "h"((uint16_t)3) : "memory");
}
__device__ __forceinline__ void tma2d_store(const CUtensorMap* tm, uint32_t src, int c0, int c1) {
  asm volatile("cp.async.bulk.tensor.2d.global.shared::cta.bulk_group [%0, {%2, %3}], [%1];" :: "l"((uint64_t)tm), "r"(src), "r"(c0), "r"(c1) : "memory");
}
__device__ __forceinline__ void bulk_g2s(uint32_t dst, const void* src, uint32_t bytes, uint32_t bar) {
  asm volatile("cp.async.bulk.shared::cluster.global.mbarrier::complete_tx::bytes [%0], [%1], %2, [%3];"
    :: "r"(dst), "l"(src), "r"(bytes), "r"(bar) : "memory");
}
__device__ __forceinline__ void l2_prefetch(const void* p, uint32_t bytes) {
  asm volatile("cp.async.bulk.prefetch.L2.global [%0], %1;" :: "l"(p), "r"(bytes) : "memory");
}
__device__ __forceinline__ void wg_fence() { asm volatile("wgmma.fence.sync.aligned;" ::: "memory"); }
__device__ __forceinline__ void wg_commit() { asm volatile("wgmma.commit_group.sync.aligned;" ::: "memory"); }
template <int N> __device__ __forceinline__ void wg_wait() { asm volatile("wgmma.wait_group.sync.aligned %0;" :: "n"(N) : "memory"); }
template <int N> __device__ __forceinline__ void fence_regs(float (&d)[N]) {
#pragma unroll
  for (int i = 0; i < N; i++) asm volatile("" : "+f"(d[i]) :: "memory");
}
template <int N> __device__ __forceinline__ void fence_u32(uint32_t (&d)[N]) {
#pragma unroll
  for (int i = 0; i < N; i++) asm volatile("" : "+r"(d[i]) :: "memory");
}
__device__ __forceinline__ uint64_t make_desc(uint32_t addr, uint32_t lbo, uint32_t sbo, uint32_t swz) {
  return (uint64_t)((addr & 0x3FFFF) >> 4) | ((uint64_t)(lbo >> 4) << 16) | ((uint64_t)(sbo >> 4) << 32) | ((uint64_t)swz << 62);
}
__device__ __forceinline__ uint32_t pack_bf16(float lo, float hi) { uint32_t r; asm("cvt.rn.bf16x2.f32 %0, %1, %2;" : "=r"(r) : "f"(hi), "f"(lo)); return r; }
__device__ __forceinline__ float bf_lo(uint32_t v) { return __uint_as_float(v << 16); }
__device__ __forceinline__ float bf_hi(uint32_t v) { return __uint_as_float(v & 0xFFFF0000u); }
__device__ __forceinline__ float bf_round(float v) { return bf_lo(pack_bf16(v, 0.f)); }
__device__ __forceinline__ uint32_t bf2_mul(uint32_t a, uint32_t b) { uint32_t r; asm("mul.rn.bf16x2 %0, %1, %2;" : "=r"(r) : "r"(a), "r"(b)); return r; }
__device__ __forceinline__ uint32_t bf2_fma(uint32_t a, uint32_t b, uint32_t c) { uint32_t r; asm("fma.rn.bf16x2 %0, %1, %2, %3;" : "=r"(r) : "r"(a), "r"(b), "r"(c)); return r; }
__device__ __forceinline__ uint32_t bf2_max(uint32_t a, uint32_t b) { uint32_t r; asm("max.bf16x2 %0, %1, %2;" : "=r"(r) : "r"(a), "r"(b)); return r; }
__device__ __forceinline__ uint32_t bf2_add(uint32_t a, uint32_t b) { uint32_t r; asm("add.rn.bf16x2 %0, %1, %2;" : "=r"(r) : "r"(a), "r"(b)); return r; }
__device__ __forceinline__ uint32_t bf2_sub(uint32_t a, uint32_t b) { uint32_t r; asm("sub.rn.bf16x2 %0, %1, %2;" : "=r"(r) : "r"(a), "r"(b)); return r; }
__device__ __forceinline__ float ex2(float x) { float r; asm("ex2.approx.ftz.f32 %0, %1;" : "=f"(r) : "f"(x)); return r; }
__device__ __forceinline__ float rcp(float x) { float r; asm("rcp.approx.ftz.f32 %0, %1;" : "=f"(r) : "f"(x)); return r; }
__device__ __forceinline__ float tanh_fast(float x) { float r; asm("tanh.approx.f32 %0, %1;" : "=f"(r) : "f"(x)); return r; }
__device__ __forceinline__ float swiglu(float g, float u) { const float gh = 0.5f * g, w = gh * u; return fmaf(w, tanh_fast(gh), w); }
__device__ __forceinline__ void stsm_x4(uint32_t addr, uint32_t r0, uint32_t r1, uint32_t r2, uint32_t r3) {
  asm volatile("stmatrix.sync.aligned.m8n8.x4.shared.b16 [%0], {%1, %2, %3, %4};" :: "r"(addr), "r"(r0), "r"(r1), "r"(r2), "r"(r3) : "memory");
}
__device__ __forceinline__ void sts128(uint32_t addr, uint32_t a, uint32_t b, uint32_t c, uint32_t d) {
  asm volatile("st.shared.v4.b32 [%0], {%1, %2, %3, %4};" :: "r"(addr), "r"(a), "r"(b), "r"(c), "r"(d) : "memory");
}
__device__ __forceinline__ void lds128(uint32_t addr, uint32_t& a, uint32_t& b, uint32_t& c, uint32_t& d) {
  asm volatile("ld.shared.v4.b32 {%0, %1, %2, %3}, [%4];" : "=r"(a), "=r"(b), "=r"(c), "=r"(d) : "r"(addr) : "memory");
}

__device__ __forceinline__ void mma16816(float (&d)[4], uint32_t a0, uint32_t a1, uint32_t a2, uint32_t a3, uint32_t b0, uint32_t b1) {
  asm("mma.sync.aligned.m16n8k16.row.col.f32.bf16.bf16.f32 {%0, %1, %2, %3}, {%4, %5, %6, %7}, {%8, %9}, {%0, %1, %2, %3};"
      : "+f"(d[0]), "+f"(d[1]), "+f"(d[2]), "+f"(d[3]) : "r"(a0), "r"(a1), "r"(a2), "r"(a3), "r"(b0), "r"(b1));
}

__device__ __forceinline__ void wgmma_ss_n160_tb(float (&d)[80], uint64_t da, uint64_t db, int sd) {
  asm volatile("{\n.reg .pred p;\nsetp.ne.b32 p, %82, 0;\n"
    "wgmma.mma_async.sync.aligned.m64n160k16.f32.bf16.bf16 {%0, %1, %2, %3, %4, %5, %6, %7, %8, %9, %10, %11, %12, %13, %14, %15, %16, %17, %18, %19, %20, %21, %22, %23, %24, %25, %26, %27, %28, %29, %30, %31, %32, %33, %34, %35, %36, %37, %38, %39, %40, %41, %42, %43, %44, %45, %46, %47, %48, %49, %50, %51, %52, %53, %54, %55, %56, %57, %58, %59, %60, %61, %62, %63, %64, %65, %66, %67, %68, %69, %70, %71, %72, %73, %74, %75, %76, %77, %78, %79}, %80, %81, p, 1, 1, 0, 1;\n}\n"
    : "+f"(d[0]), "+f"(d[1]), "+f"(d[2]), "+f"(d[3]), "+f"(d[4]), "+f"(d[5]), "+f"(d[6]), "+f"(d[7]), "+f"(d[8]), "+f"(d[9]), "+f"(d[10]), "+f"(d[11]), "+f"(d[12]), "+f"(d[13]), "+f"(d[14]), "+f"(d[15]), "+f"(d[16]), "+f"(d[17]), "+f"(d[18]), "+f"(d[19]), "+f"(d[20]), "+f"(d[21]), "+f"(d[22]), "+f"(d[23]), "+f"(d[24]), "+f"(d[25]), "+f"(d[26]), "+f"(d[27]), "+f"(d[28]), "+f"(d[29]), "+f"(d[30]), "+f"(d[31]), "+f"(d[32]), "+f"(d[33]), "+f"(d[34]), "+f"(d[35]), "+f"(d[36]), "+f"(d[37]), "+f"(d[38]), "+f"(d[39]), "+f"(d[40]), "+f"(d[41]), "+f"(d[42]), "+f"(d[43]), "+f"(d[44]), "+f"(d[45]), "+f"(d[46]), "+f"(d[47]), "+f"(d[48]), "+f"(d[49]), "+f"(d[50]), "+f"(d[51]), "+f"(d[52]), "+f"(d[53]), "+f"(d[54]), "+f"(d[55]), "+f"(d[56]), "+f"(d[57]), "+f"(d[58]), "+f"(d[59]), "+f"(d[60]), "+f"(d[61]), "+f"(d[62]), "+f"(d[63]), "+f"(d[64]), "+f"(d[65]), "+f"(d[66]), "+f"(d[67]), "+f"(d[68]), "+f"(d[69]), "+f"(d[70]), "+f"(d[71]), "+f"(d[72]), "+f"(d[73]), "+f"(d[74]), "+f"(d[75]), "+f"(d[76]), "+f"(d[77]), "+f"(d[78]), "+f"(d[79])
    : "l"(da), "l"(db), "r"(sd));
}
__device__ __forceinline__ void wgmma_ss_n96_tb(float (&d)[48], uint64_t da, uint64_t db, int sd) {
  asm volatile("{\n.reg .pred p;\nsetp.ne.b32 p, %50, 0;\n"
    "wgmma.mma_async.sync.aligned.m64n96k16.f32.bf16.bf16 {%0, %1, %2, %3, %4, %5, %6, %7, %8, %9, %10, %11, %12, %13, %14, %15, %16, %17, %18, %19, %20, %21, %22, %23, %24, %25, %26, %27, %28, %29, %30, %31, %32, %33, %34, %35, %36, %37, %38, %39, %40, %41, %42, %43, %44, %45, %46, %47}, %48, %49, p, 1, 1, 0, 1;\n}\n"
    : "+f"(d[0]), "+f"(d[1]), "+f"(d[2]), "+f"(d[3]), "+f"(d[4]), "+f"(d[5]), "+f"(d[6]), "+f"(d[7]), "+f"(d[8]), "+f"(d[9]), "+f"(d[10]), "+f"(d[11]), "+f"(d[12]), "+f"(d[13]), "+f"(d[14]), "+f"(d[15]), "+f"(d[16]), "+f"(d[17]), "+f"(d[18]), "+f"(d[19]), "+f"(d[20]), "+f"(d[21]), "+f"(d[22]), "+f"(d[23]), "+f"(d[24]), "+f"(d[25]), "+f"(d[26]), "+f"(d[27]), "+f"(d[28]), "+f"(d[29]), "+f"(d[30]), "+f"(d[31]), "+f"(d[32]), "+f"(d[33]), "+f"(d[34]), "+f"(d[35]), "+f"(d[36]), "+f"(d[37]), "+f"(d[38]), "+f"(d[39]), "+f"(d[40]), "+f"(d[41]), "+f"(d[42]), "+f"(d[43]), "+f"(d[44]), "+f"(d[45]), "+f"(d[46]), "+f"(d[47])
    : "l"(da), "l"(db), "r"(sd));
}
__device__ __forceinline__ void wgmma_ss_n192_tb(float (&d)[96], uint64_t da, uint64_t db, int sd) {
  asm volatile("{\n.reg .pred p;\nsetp.ne.b32 p, %98, 0;\n"
    "wgmma.mma_async.sync.aligned.m64n192k16.f32.bf16.bf16 {%0, %1, %2, %3, %4, %5, %6, %7, %8, %9, %10, %11, %12, %13, %14, %15, %16, %17, %18, %19, %20, %21, %22, %23, %24, %25, %26, %27, %28, %29, %30, %31, %32, %33, %34, %35, %36, %37, %38, %39, %40, %41, %42, %43, %44, %45, %46, %47, %48, %49, %50, %51, %52, %53, %54, %55, %56, %57, %58, %59, %60, %61, %62, %63, %64, %65, %66, %67, %68, %69, %70, %71, %72, %73, %74, %75, %76, %77, %78, %79, %80, %81, %82, %83, %84, %85, %86, %87, %88, %89, %90, %91, %92, %93, %94, %95}, %96, %97, p, 1, 1, 0, 1;\n}\n"
    : "+f"(d[0]), "+f"(d[1]), "+f"(d[2]), "+f"(d[3]), "+f"(d[4]), "+f"(d[5]), "+f"(d[6]), "+f"(d[7]), "+f"(d[8]), "+f"(d[9]), "+f"(d[10]), "+f"(d[11]), "+f"(d[12]), "+f"(d[13]), "+f"(d[14]), "+f"(d[15]), "+f"(d[16]), "+f"(d[17]), "+f"(d[18]), "+f"(d[19]), "+f"(d[20]), "+f"(d[21]), "+f"(d[22]), "+f"(d[23]), "+f"(d[24]), "+f"(d[25]), "+f"(d[26]), "+f"(d[27]), "+f"(d[28]), "+f"(d[29]), "+f"(d[30]), "+f"(d[31]), "+f"(d[32]), "+f"(d[33]), "+f"(d[34]), "+f"(d[35]), "+f"(d[36]), "+f"(d[37]), "+f"(d[38]), "+f"(d[39]), "+f"(d[40]), "+f"(d[41]), "+f"(d[42]), "+f"(d[43]), "+f"(d[44]), "+f"(d[45]), "+f"(d[46]), "+f"(d[47]), "+f"(d[48]), "+f"(d[49]), "+f"(d[50]), "+f"(d[51]), "+f"(d[52]), "+f"(d[53]), "+f"(d[54]), "+f"(d[55]), "+f"(d[56]), "+f"(d[57]), "+f"(d[58]), "+f"(d[59]), "+f"(d[60]), "+f"(d[61]), "+f"(d[62]), "+f"(d[63]), "+f"(d[64]), "+f"(d[65]), "+f"(d[66]), "+f"(d[67]), "+f"(d[68]), "+f"(d[69]), "+f"(d[70]), "+f"(d[71]), "+f"(d[72]), "+f"(d[73]), "+f"(d[74]), "+f"(d[75]), "+f"(d[76]), "+f"(d[77]), "+f"(d[78]), "+f"(d[79]), "+f"(d[80]), "+f"(d[81]), "+f"(d[82]), "+f"(d[83]), "+f"(d[84]), "+f"(d[85]), "+f"(d[86]), "+f"(d[87]), "+f"(d[88]), "+f"(d[89]), "+f"(d[90]), "+f"(d[91]), "+f"(d[92]), "+f"(d[93]), "+f"(d[94]), "+f"(d[95])
    : "l"(da), "l"(db), "r"(sd));
}
__device__ __forceinline__ void wgmma_ss_n56_tb(float (&d)[28], uint64_t da, uint64_t db, int sd) {
  asm volatile("{\n.reg .pred p;\nsetp.ne.b32 p, %30, 0;\n"
    "wgmma.mma_async.sync.aligned.m64n56k16.f32.bf16.bf16 {%0, %1, %2, %3, %4, %5, %6, %7, %8, %9, %10, %11, %12, %13, %14, %15, %16, %17, %18, %19, %20, %21, %22, %23, %24, %25, %26, %27}, %28, %29, p, 1, 1, 0, 1;\n}\n"
    : "+f"(d[0]), "+f"(d[1]), "+f"(d[2]), "+f"(d[3]), "+f"(d[4]), "+f"(d[5]), "+f"(d[6]), "+f"(d[7]), "+f"(d[8]), "+f"(d[9]), "+f"(d[10]), "+f"(d[11]), "+f"(d[12]), "+f"(d[13]), "+f"(d[14]), "+f"(d[15]), "+f"(d[16]), "+f"(d[17]), "+f"(d[18]), "+f"(d[19]), "+f"(d[20]), "+f"(d[21]), "+f"(d[22]), "+f"(d[23]), "+f"(d[24]), "+f"(d[25]), "+f"(d[26]), "+f"(d[27])
    : "l"(da), "l"(db), "r"(sd));
}
__device__ __forceinline__ void wgmma_rs_n64(float (&d)[32], uint32_t a0, uint32_t a1, uint32_t a2, uint32_t a3, uint64_t db, int sd) {
  asm volatile("{\n.reg .pred p;\nsetp.ne.b32 p, %37, 0;\n"
    "wgmma.mma_async.sync.aligned.m64n64k16.f32.bf16.bf16 {%0, %1, %2, %3, %4, %5, %6, %7, %8, %9, %10, %11, %12, %13, %14, %15, %16, %17, %18, %19, %20, %21, %22, %23, %24, %25, %26, %27, %28, %29, %30, %31}, {%32, %33, %34, %35}, %36, p, 1, 1, 0;\n}\n"
    : "+f"(d[0]), "+f"(d[1]), "+f"(d[2]), "+f"(d[3]), "+f"(d[4]), "+f"(d[5]), "+f"(d[6]), "+f"(d[7]), "+f"(d[8]), "+f"(d[9]), "+f"(d[10]), "+f"(d[11]), "+f"(d[12]), "+f"(d[13]), "+f"(d[14]), "+f"(d[15]), "+f"(d[16]), "+f"(d[17]), "+f"(d[18]), "+f"(d[19]), "+f"(d[20]), "+f"(d[21]), "+f"(d[22]), "+f"(d[23]), "+f"(d[24]), "+f"(d[25]), "+f"(d[26]), "+f"(d[27]), "+f"(d[28]), "+f"(d[29]), "+f"(d[30]), "+f"(d[31])
    : "r"(a0), "r"(a1), "r"(a2), "r"(a3), "l"(db), "r"(sd));
}
__device__ __forceinline__ void wgmma_rs_n64_z(float (&d)[32], uint32_t a0, uint32_t a1, uint32_t a2, uint32_t a3, uint64_t db) {
  asm volatile("{\n.reg .pred p;\nsetp.ne.b32 p, 0, 0;\n"
    "wgmma.mma_async.sync.aligned.m64n64k16.f32.bf16.bf16 {%0, %1, %2, %3, %4, %5, %6, %7, %8, %9, %10, %11, %12, %13, %14, %15, %16, %17, %18, %19, %20, %21, %22, %23, %24, %25, %26, %27, %28, %29, %30, %31}, {%32, %33, %34, %35}, %36, p, 1, 1, 0;\n}\n"
    : "=f"(d[0]), "=f"(d[1]), "=f"(d[2]), "=f"(d[3]), "=f"(d[4]), "=f"(d[5]), "=f"(d[6]), "=f"(d[7]), "=f"(d[8]), "=f"(d[9]), "=f"(d[10]), "=f"(d[11]), "=f"(d[12]), "=f"(d[13]), "=f"(d[14]), "=f"(d[15]), "=f"(d[16]), "=f"(d[17]), "=f"(d[18]), "=f"(d[19]), "=f"(d[20]), "=f"(d[21]), "=f"(d[22]), "=f"(d[23]), "=f"(d[24]), "=f"(d[25]), "=f"(d[26]), "=f"(d[27]), "=f"(d[28]), "=f"(d[29]), "=f"(d[30]), "=f"(d[31])
    : "r"(a0), "r"(a1), "r"(a2), "r"(a3), "l"(db));
}
__device__ __forceinline__ void wgmma_rs_n56_tb(float (&d)[28], uint32_t a0, uint32_t a1, uint32_t a2, uint32_t a3, uint64_t db, int sd) {
  asm volatile("{\n.reg .pred p;\nsetp.ne.b32 p, %33, 0;\n"
    "wgmma.mma_async.sync.aligned.m64n56k16.f32.bf16.bf16 {%0, %1, %2, %3, %4, %5, %6, %7, %8, %9, %10, %11, %12, %13, %14, %15, %16, %17, %18, %19, %20, %21, %22, %23, %24, %25, %26, %27}, {%28, %29, %30, %31}, %32, p, 1, 1, 1;\n}\n"
    : "+f"(d[0]), "+f"(d[1]), "+f"(d[2]), "+f"(d[3]), "+f"(d[4]), "+f"(d[5]), "+f"(d[6]), "+f"(d[7]), "+f"(d[8]), "+f"(d[9]), "+f"(d[10]), "+f"(d[11]), "+f"(d[12]), "+f"(d[13]), "+f"(d[14]), "+f"(d[15]), "+f"(d[16]), "+f"(d[17]), "+f"(d[18]), "+f"(d[19]), "+f"(d[20]), "+f"(d[21]), "+f"(d[22]), "+f"(d[23]), "+f"(d[24]), "+f"(d[25]), "+f"(d[26]), "+f"(d[27])
    : "r"(a0), "r"(a1), "r"(a2), "r"(a3), "l"(db), "r"(sd));
}
__device__ __forceinline__ void wgmma_rs_n32_tb(float (&d)[16], uint32_t a0, uint32_t a1, uint32_t a2, uint32_t a3, uint64_t db, int sd) {
  asm volatile("{\n.reg .pred p;\nsetp.ne.b32 p, %21, 0;\n"
    "wgmma.mma_async.sync.aligned.m64n32k16.f32.bf16.bf16 {%0, %1, %2, %3, %4, %5, %6, %7, %8, %9, %10, %11, %12, %13, %14, %15}, {%16, %17, %18, %19}, %20, p, 1, 1, 1;\n}\n"
    : "+f"(d[0]), "+f"(d[1]), "+f"(d[2]), "+f"(d[3]), "+f"(d[4]), "+f"(d[5]), "+f"(d[6]), "+f"(d[7]), "+f"(d[8]), "+f"(d[9]), "+f"(d[10]), "+f"(d[11]), "+f"(d[12]), "+f"(d[13]), "+f"(d[14]), "+f"(d[15])
    : "r"(a0), "r"(a1), "r"(a2), "r"(a3), "l"(db), "r"(sd));
}

template <int V> struct IC { static constexpr int value = V; };
struct Ring { uint32_t slot, phase; __device__ __forceinline__ void next() { if (++slot == NSTAGE) { slot = 0; phase ^= 1; } } };

template <int N, bool LAST>
__device__ __forceinline__ void gemm_pass(float (&acc)[N / 2], uint64_t descA0, uint64_t descB0, uint32_t bars, Ring& rg, int lane) {
  uint32_t prev = 0;
  mbar_wait(bars + 8 * (B_FULL + rg.slot), rg.phase);
  uint64_t dA = descA0, dB = descB0 + (uint64_t)(rg.slot * (RING_STAGE >> 4));
#pragma unroll 1
  for (int kb = 0; kb < 14; kb++) {
    wg_fence();
    if constexpr (N == 192) wgmma_ss_n192_tb(acc, dA, dB, kb > 0); else wgmma_ss_n160_tb(acc, dA, dB, kb > 0);
    wg_commit();
    wg_wait<1>();
    if (kb > 0) arrive_pair(bars + 8 * (B_EMPTY + prev), lane);
    if (LAST && kb > 0 && !(kb & 1)) arrive_pair(bars + 8 * (B_XDEAD + (kb >> 1) - 1), lane);
    prev = rg.slot;
    rg.next();
    wg_fence();
    if constexpr (N == 192) wgmma_ss_n192_tb(acc, dA + 2, dB + 64, 1); else wgmma_ss_n160_tb(acc, dA + 2, dB + 64, 1);
    wg_commit();
    dA += (kb & 1) ? 1020 : 4;
    dB = descB0 + (uint64_t)(rg.slot * (RING_STAGE >> 4));
    if (kb < 13) mbar_wait(bars + 8 * (B_FULL + rg.slot), rg.phase);
    wg_wait<1>();
  }
  wg_wait<0>();
  arrive_pair(bars + 8 * (B_EMPTY + prev), lane);
  if (LAST) arrive_pair(bars + 8 * (B_XDEAD + 6), lane);
  fence_regs(acc);
}
__device__ __forceinline__ void gemm_pass_96(float (&acc)[48], uint64_t descA0, uint64_t descB0, uint32_t bars, Ring& rg, int lane) {
  uint32_t prev = 0;
#pragma unroll 1
  for (int kb = 0; kb < 7; kb++) {
    mbar_wait(bars + 8 * (B_FULL + rg.slot), rg.phase);
    const uint64_t dA = descA0 + (uint64_t)(kb * 1024);
    const uint64_t dB = descB0 + (uint64_t)(rg.slot * (RING_STAGE >> 4));
    wg_fence();
#pragma unroll
    for (int s = 0; s < 4; s++) wgmma_ss_n96_tb(acc, dA + 2 * s, dB + (s >> 1) * 384 + (s & 1) * 64, kb > 0 || s > 0);
    wg_commit();
    if (kb > 0) { wg_wait<1>(); arrive_pair(bars + 8 * (B_EMPTY + prev), lane); }
    prev = rg.slot;
    rg.next();
  }
  wg_wait<0>();
  arrive_pair(bars + 8 * (B_EMPTY + prev), lane);
  fence_regs(acc);
}

constexpr float LOG2E = 1.4426950408889634f;
constexpr uint32_t SCALE_HI2 = 0x3E413E41u;
constexpr uint32_t SCALE_LO2 = 0x3A053A05u;

struct SmStat { float al0, al1, n0, n1; };
template <int K0, int K1> __device__ __forceinline__ void sm_pack(const float (&s)[32], uint32_t (&t)[16]) {
#pragma unroll
  for (int k = K0; k < K1; k++) { const uint32_t u = pack_bf16(s[2 * k], s[2 * k + 1]); t[k] = bf2_fma(u, SCALE_HI2, bf2_mul(u, SCALE_LO2)); }
#pragma unroll
  for (int k = K0; k < K1; k++) asm volatile("" : "+r"(t[k]) :: "memory");
}
__device__ __forceinline__ void sm_mask(uint32_t (&t)[16], const uint32_t (&mk)[8], bool edge) {
  if (!edge) {
#pragma unroll
    for (int k = 0; k < 16; k++) if (k != 1) asm("lop3.b32 %0, %0, %1, 0xFF80FF80, 0xE2;" : "+r"(t[k]) : "r"(mk[(k >> 1) - (k & 1)]));
  } else {
    t[1] = 0xFF80FF80u;
#pragma unroll
    for (int k = 0; k < 16; k++) if (k != 1) asm("lop3.b32 %0, %0, %1, 0xFF80FF80, 0xB8;" : "+r"(t[k]) : "r"(mk[(k >> 1) - (k & 1)]));
  }
}
__device__ __forceinline__ uint32_t sm_max(const uint32_t (&t)[16]) {
  uint32_t a = bf2_max(bf2_max(bf2_max(t[0], t[2]), bf2_max(t[4], t[6])), bf2_max(bf2_max(t[8], t[10]), bf2_max(t[12], t[14])));
  uint32_t b = bf2_max(bf2_max(bf2_max(t[1], t[3]), bf2_max(t[5], t[7])), bf2_max(bf2_max(t[9], t[11]), bf2_max(t[13], t[15])));
  uint32_t r = bf2_max(__byte_perm(a, b, 0x5410), __byte_perm(a, b, 0x7632));
  return bf2_max(r, __shfl_xor_sync(0xffffffffu, r, 1));
}
__device__ __forceinline__ void sm_stat(uint32_t r, uint32_t& mrun, bool valid, SmStat& st) {
  r = bf2_max(r, __shfl_xor_sync(0xffffffffu, r, 2));
  const uint32_t mnew = valid ? bf2_max(mrun, r) : mrun;
  const float m0 = bf_lo(mnew), m1 = bf_hi(mnew);
  st.al0 = ex2((bf_lo(mrun) - m0) * LOG2E); st.al1 = ex2((bf_hi(mrun) - m1) * LOG2E);
  mrun = mnew;
  st.n0 = valid ? -m0 * LOG2E : -INFINITY; st.n1 = valid ? -m1 * LOG2E : -INFINITY;
  asm volatile("" : "+f"(st.al0), "+f"(st.al1), "+f"(st.n0), "+f"(st.n1) :: "memory");
}
template <int K0, int K1> __device__ __forceinline__ void sm_exp(const uint32_t (&t)[16], uint32_t (&p)[16], float n0, float n1) {
#pragma unroll
  for (int k = K0; k < K1; k++) {
    const float n = (k & 1) ? n1 : n0;
    p[k] = pack_bf16(ex2(fmaf(bf_lo(t[k]), LOG2E, n)), ex2(fmaf(bf_hi(t[k]), LOG2E, n)));
  }
#pragma unroll
  for (int k = K0; k < K1; k++) asm volatile("" : "+r"(p[k]) :: "memory");
}
__device__ __forceinline__ void sm_rescale(float (&o)[16], const SmStat& st) {
#pragma unroll
  for (int k = 0; k < 4; k++) { o[4 * k] *= st.al0; o[4 * k + 1] *= st.al0; o[4 * k + 2] *= st.al1; o[4 * k + 3] *= st.al1; }
  fence_regs(o);
}
template <bool FIRST = false>
__device__ __forceinline__ void issue_s(float (&s)[32], const uint32_t (&qf)[8], uint64_t dk) {
  wg_fence();
  if constexpr (FIRST) wgmma_rs_n64_z(s, qf[0], qf[1], qf[2], qf[3], dk);
  else wgmma_rs_n64(s, qf[0], qf[1], qf[2], qf[3], dk, 0);
  wgmma_rs_n64(s, qf[4], qf[5], qf[6], qf[7], dk + 2, 1);
  wg_commit();
}
__device__ __forceinline__ void issue_pv(float (&o)[16], uint32_t (&p)[16], uint64_t dv) {
  fence_regs(o);
  wg_fence();
#pragma unroll
  for (int k = 0; k < 4; k++) wgmma_rs_n32_tb(o, p[4 * k], p[4 * k + 1], p[4 * k + 2], p[4 * k + 3], dv + 64 * k, 1);
  wg_commit();
}
__device__ __forceinline__ void attn_block(float (&s)[32], const uint32_t (&dq)[8], uint64_t dk, float (&op)[16], uint32_t (&pp)[16], uint64_t dv,
                                           uint32_t (&tn)[16], uint32_t& mn, SmStat& stn, bool validn, bool masked, bool flip,
                                           const uint32_t (&tc)[16], uint32_t (&pc)[16], float (&oc)[16], const SmStat& stc,
                                           const uint32_t (&mk)[8], int zero, uint32_t bars) {
  const float n0 = stc.n0, n1 = stc.n1;
  issue_pv(op, pp, dv);
  sm_pack<0, 16>(s, tn); sm_exp<0, 5>(tc, pc, n0, n1);
  issue_s(s, dq, dk);
  if (masked) sm_mask(tn, mk, flip);
  sm_stat(sm_max(tn), mn, validn, stn);
  sm_rescale(oc, stc); sm_exp<5, 16>(tc, pc, n0, n1);
  {
    uint32_t dep = __float_as_uint(stn.n0) ^ __float_as_uint(stn.al1) ^ __float_as_uint(oc[0]) ^ __float_as_uint(oc[15]);
#pragma unroll
    for (int k = 0; k < 16; k++) dep ^= pc[k];
    asm volatile("{\n.reg .pred p;\nsetp.ne.u32 p, %0, 0;\n@p st.volatile.shared.u32 [%1], %0;\n}\n" :: "r"(dep & zero), "r"(bars + SM_TAG + 4) : "memory");
  }
  wg_wait<0>(); fence_regs(s); fence_regs(op);
}

struct TMaps { CUtensorMap qkv, w1a, w3a, w1c, w3c, w2_64, w2_48, wo, o, ost, x, out; };

__global__ void __cluster_dims__(2, 1, 1) __launch_bounds__(512, 1) fused_kernel(
    const __grid_constant__ TMaps tm,
    const __nv_bfloat16* __restrict__ x, const uint8_t* __restrict__ wqkv, const uint8_t* __restrict__ wo,
    const uint8_t* __restrict__ w1, const uint8_t* __restrict__ w3, const uint8_t* __restrict__ w2,
    __nv_bfloat16* __restrict__ out, const int zero) {
  extern __shared__ uint8_t smem_raw[];
  const uint32_t sb = (smem_u32(smem_raw) + 1023u) & ~1023u;
  const uint32_t bars = sb + SM_BAR;
  const int tid = threadIdx.x, lane = tid & 31;
  const int warp = __shfl_sync(0xffffffffu, tid >> 5, 0);
  const int ti = blockIdx.x & 15, tj = blockIdx.x >> 4;
  const int rank = ti & 1;

  if (tid == 448) l2_prefetch(reinterpret_cast<const uint8_t*>(x) + (size_t)(ti * 128 + tj * 16) * (DM * 2), 16 * DM * 2);
  if (warp == 15) {
    if (lane == 0) {
      asm volatile("prefetch.tensormap [%0];" :: "l"((uint64_t)&tm.x) : "memory");
#pragma unroll
      for (int k = 0; k < 4; k++) mbar_init(bars + 8 * (B_X + k), 1);
      asm volatile("fence.mbarrier_init.release.cluster;" ::: "memory");
#pragma unroll 1
      for (int gq = 0; gq < 4; gq++) {
        mbar_expect_tx(bars + 8 * (B_X + gq), 28672);
#pragma unroll
        for (int kb = 0; kb < 7; kb++) tma2d(sb + SM_XN + kb * 16384 + gq * 4096, &tm.x, bars + 8 * (B_X + gq), 64 * kb, ti * 128 + 32 * gq);
        if (gq == 0) asm volatile("barrier.cluster.arrive.relaxed;" ::: "memory");
      }
    } else {
      asm volatile("barrier.cluster.arrive.relaxed;" ::: "memory");
    }
    __syncwarp();
  } else {
    if (lane == 0 && warp < 8) {
      const int cnt = (int)(BAR_COUNTS >> (8 * warp)) & 0xFF;
#pragma unroll
      for (int k = 0; k < 8; k++) mbar_init(bars + 64 * warp + 8 * k, cnt);
      asm volatile("fence.mbarrier_init.release.cluster;" ::: "memory");
    } else if (lane == 0 && warp < 14) {
      asm volatile("prefetch.tensormap [%0];" :: "l"((uint64_t)(&tm.qkv + 2 * (warp - 8))) : "memory");
      asm volatile("prefetch.tensormap [%0];" :: "l"((uint64_t)(&tm.qkv + 2 * (warp - 8) + 1)) : "memory");
    } else if (lane == 0) {
      mbar_init(bars + 8 * B_QKV2, 8); mbar_init(bars + 8 * B_O0, 8); mbar_init(bars + 8 * B_O1, 8); mbar_init(bars + 8 * B_OE, 4); mbar_init(bars + 8 * B_LN, 8); mbar_init(bars + 8 * (B_LN + 1), 8);
      asm volatile("fence.mbarrier_init.release.cluster;" ::: "memory");
    }
    __syncwarp();
    asm volatile("barrier.cluster.arrive.relaxed;" ::: "memory");
  }
  if (tid == 448) { const uint32_t e = ld_relaxed(&g_epoch); asm volatile("st.shared.u32 [%0], %1;" :: "r"(bars + SM_TAG), "r"(e) : "memory"); }
  asm volatile("barrier.cluster.wait.acquire;" ::: "memory");
  if (tid == 0) PROF(2);
  if (lane == 0 && warp >= 8 && warp < 15) {
    const int k = warp - 8;
    mbar_wait(bars + 8 * (B_X + 1), 0);
    if (k < NSTAGE) {
      tma5d_mc(sb + SM_RING + k * RING_STAGE + rank * 6144, &tm.qkv, bars + 8 * (B_FULL + k), 0, 64 * k + 32 * rank, 0, 0, tj);
      mbar_expect_tx(bars + 8 * (B_FULL + k), 12288);
    } else {
      l2_prefetch(wqkv + (size_t)blockIdx.x * 9408, 9408);
      mbar_wait(bars + 8 * (B_X + 3), 0);
      l2_prefetch(w1 + (size_t)blockIdx.x * 12544, 12544);
      l2_prefetch(w3 + (size_t)blockIdx.x * 12544, 12544);
    }
  }
  __syncwarp();
  {
    const uint32_t a0 = sb + SM_XN + (warp * 8 + (lane >> 3)) * 128 + (((lane & 7) ^ (lane >> 3)) << 4), a1 = (a0 ^ 64) + 512;
    uint32_t w[7][8];
    mbar_wait(bars + 8 * (B_X + (warp >> 2)), 0);
    if (lane == 0) PROF2(3, 16 + warp);
#pragma unroll
    for (int kb = 0; kb < 7; kb++) {
      lds128(a0 + kb * 16384, w[kb][0], w[kb][1], w[kb][2], w[kb][3]);
      lds128(a1 + kb * 16384, w[kb][4], w[kb][5], w[kb][6], w[kb][7]);
    }
    float cs[4] = {0.f, 0.f, 0.f, 0.f}, cp[4] = {0.f, 0.f, 0.f, 0.f}, cq[4] = {0.f, 0.f, 0.f, 0.f};
    float ds[4] = {0.f, 0.f, 0.f, 0.f}, dp[4] = {0.f, 0.f, 0.f, 0.f}, dq[4] = {0.f, 0.f, 0.f, 0.f};
#pragma unroll
    for (int kb = 0; kb < 7; kb++) {
      mma16816(cs, w[kb][0], w[kb][4], w[kb][1], w[kb][5], 0x3F803F80u, 0x3F803F80u);
      mma16816(cp, w[kb][0], w[kb][4], w[kb][1], w[kb][5], w[kb][0], w[kb][1]);
      mma16816(cq, w[kb][0], w[kb][4], w[kb][1], w[kb][5], w[kb][4], w[kb][5]);
      mma16816(ds, w[kb][2], w[kb][6], w[kb][3], w[kb][7], 0x3F803F80u, 0x3F803F80u);
      mma16816(dp, w[kb][2], w[kb][6], w[kb][3], w[kb][7], w[kb][2], w[kb][3]);
      mma16816(dq, w[kb][2], w[kb][6], w[kb][3], w[kb][7], w[kb][6], w[kb][7]);
    }
    const bool gi = (lane >> 2) & 1, od = lane & 1;
    const int dsrc = (lane & ~3) | (lane >> 3);
    float u0 = __shfl_sync(0xffffffffu, gi ? cp[1] + dp[1] : cp[0] + dp[0], dsrc);
    float u1 = __shfl_sync(0xffffffffu, gi ? cq[3] + dq[3] : cq[2] + dq[2], dsrc);
    float ts = od ? cs[2] + ds[2] : cs[0] + ds[0], us = od ? u1 : u0;
    ts += __shfl_xor_sync(0xffffffffu, ts, 4); us += __shfl_xor_sync(0xffffffffu, us, 4);
    const float mean = ts * (1.0f / DM);
    float var = fmaf(-mean, mean, us * (1.0f / DM));
    if (__any_sync(0xffffffffu, !(mean * mean <= 16.0f * var))) {
      const float mo = __shfl_xor_sync(0xffffffffu, mean, 1), me0 = od ? mo : mean, me1 = od ? mean : mo;
      float q0 = 0.f, q1 = 0.f;
#pragma unroll 1
      for (int kb = 0; kb < 7; kb++) {
        uint32_t y[8];
        lds128(a0 + kb * 16384, y[0], y[1], y[2], y[3]);
        lds128(a1 + kb * 16384, y[4], y[5], y[6], y[7]);
#pragma unroll
        for (int e = 0; e < 4; e++) {
          const float a = bf_lo(y[e]) - me0, b = bf_hi(y[e]) - me0, c = bf_lo(y[4 + e]) - me1, d = bf_hi(y[4 + e]) - me1;
          q0 = fmaf(a, a, fmaf(b, b, q0)); q1 = fmaf(c, c, fmaf(d, d, q1));
        }
      }
#pragma unroll
      for (int o = 1; o < 8; o <<= 1) { q0 += __shfl_xor_sync(0xffffffffu, q0, o); q1 += __shfl_xor_sync(0xffffffffu, q1, o); }
      var = (od ? q1 : q0) * (1.0f / DM);
    }
    float sd;
    asm("sqrt.approx.f32 %0, %1;" : "=f"(sd) : "f"(bf_round(bf_round(fmaxf(var, 0.f)) + 1e-5f)));
    const float rinv = rcp(bf_round(sd)), rhi = bf_round(rinv);
    const uint32_t pm = pack_bf16(mean, rhi), pl = pack_bf16(rinv - rhi, rinv - rhi);
    const uint32_t pmo = __shfl_xor_sync(0xffffffffu, pm, 1), plo = __shfl_xor_sync(0xffffffffu, pl, 1);
    const uint32_t m0 = od ? pmo : pm, m1 = od ? pm : pmo, l0 = od ? plo : pl, l1 = od ? pl : plo;
    const uint32_t mb0 = __byte_perm(m0, 0, 0x1010), rh0 = __byte_perm(m0, 0, 0x3232), mb1 = __byte_perm(m1, 0, 0x1010), rh1 = __byte_perm(m1, 0, 0x3232);
#pragma unroll
    for (int kb = 0; kb < 7; kb++) {
#pragma unroll
      for (int e = 0; e < 4; e++) {
        const uint32_t d0 = bf2_sub(w[kb][e], mb0), d1 = bf2_sub(w[kb][4 + e], mb1);
        w[kb][e] = bf2_fma(d0, rh0, bf2_mul(d0, l0)); w[kb][4 + e] = bf2_fma(d1, rh1, bf2_mul(d1, l1));
      }
      sts128(a0 + kb * 16384, w[kb][0], w[kb][1], w[kb][2], w[kb][3]);
      sts128(a1 + kb * 16384, w[kb][4], w[kb][5], w[kb][6], w[kb][7]);
    }
  }
  if (lane == 0) PROF2(3, warp);
  fence_proxy_async_smem();
  __syncwarp();
  if (lane == 0) mbar_arrive(bars + 8 * (B_LN + (warp >> 3)));
  auto read_epoch = [&]() {
    mbar_wait(bars + 8 * (B_LN + 1), 0);
    uint32_t e;
    asm volatile("ld.shared.u32 %0, [%1];" : "=r"(e) : "r"(bars + SM_TAG) : "memory");
    return e;
  };

  const int wg = warp >> 2;
  if (wg == 2) {
    asm volatile("setmaxnreg.inc.sync.aligned.u32 168;");
    const int w4 = warp & 3, g = lane >> 2, q = lane & 3;
    uint32_t mk[8];
    {
      const int thr = 16 * w4 + g - 2 * q;
#pragma unroll
      for (int j = 0; j < 8; j++) mk[j] = (8 * j <= thr ? 0x0000FFFFu : 0u) | (8 * j + 1 <= thr ? 0xFFFF0000u : 0u);
    }
    const uint64_t dkv0 = make_desc(sb + SM_KV, 16, 512, 2);
    const int t128 = tid - 256;
    auto KD = [&](int n) { return dkv0 + (uint64_t)((n & 3) * 512); };
    auto VD = [&](int n) { return dkv0 + (uint64_t)((n & 3) * 512 + 256); };
    auto WAITKV = [&](int n) { mbar_wait(bars + 8 * (B_KVFULL + (n & 3)), (n >> 2) & 1); };
    auto RELKV = [&](int n) { if (lane == 0) mbar_arrive(bars + 8 * (B_KVEMPTY + (n & 3))); };
    auto finish = [&](const float (&o)[16], int hh, int unit) {
      const int srcl = (lane & ~3) | (hh ? 0 : 2);
      const float la = rcp(__shfl_sync(0xffffffffu, hh ? o[0] : o[12], srcl)), lb = rcp(__shfl_sync(0xffffffffu, hh ? o[2] : o[14], srcl));
      uint32_t r[8];
#pragma unroll
      for (int b = 0; b < 4; b++) { r[2 * b] = pack_bf16(o[4 * b] * la, o[4 * b + 1] * la); r[2 * b + 1] = pack_bf16(o[4 * b + 2] * lb, o[4 * b + 3] * lb); }
      if (hh == 0 && q >= 2) { r[6] = 0; r[7] = 0; }
      if (hh == 1 && q < 2) { r[0] = 0; r[1] = 0; }
      const uint32_t stg = hh ? sb + SM_KV + unit * 4096 + w4 * 1024 : sb + SM_STG + (unit * 4 + w4) * 1024;
      const uint32_t base = stg + (lane & 15) * 64, sw = (lane >> 1) & 3, chb = lane >> 4;
      stsm_x4(base + (((0 + chb) ^ sw) << 4), r[0], r[1], r[2], r[3]);
      stsm_x4(base + (((2 + chb) ^ sw) << 4), r[4], r[5], r[6], r[7]);
      fence_proxy_async_smem();
      __syncwarp();
      if (lane == 0) mbar_arrive(bars + 8 * (B_O0 + hh));
    };
    auto load_q1 = [&](uint32_t (&qf)[8], int unit) {
      const uint4* src = reinterpret_cast<const uint4*>(g_q + (size_t)(ti * NJ + tj) * 8192 + unit * 4096) + t128;
      const uint4 a = __ldcg(src), b = __ldcg(src + 128);
      qf[0] = a.x; qf[1] = a.y; qf[2] = a.z; qf[3] = a.w; qf[4] = b.x; qf[5] = b.y; qf[6] = b.z; qf[7] = b.w;
    };
    float sx[32], o0[16], o1[16];
    uint32_t ta[16], tb[16], pa[16], pb[16], qa[8], qb[8], m0, m1 = 0xFF80FF80u;
    SmStat sta, stb;
#pragma unroll
    for (int k = 0; k < 16; k++) { o0[k] = 0.f; o1[k] = 0.f; pb[k] = 0u; }
    mbar_wait_sleep(bars + 8 * (B_KVFULL + 0), 0);
    {
      const uint32_t qs = sb + SM_KV + 3 * 8192 + t128 * 16;
      lds128(qs, qb[0], qb[1], qb[2], qb[3]); lds128(qs + 2048, qb[4], qb[5], qb[6], qb[7]);
      lds128(qs + 4096, qa[0], qa[1], qa[2], qa[3]); lds128(qs + 6144, qa[4], qa[5], qa[6], qa[7]);
    }
    issue_s<true>(sx, qa, KD(0));
    fence_u32(qb);
    __syncwarp();
    RELKV(3);
    WAITKV(1);
    wg_wait<0>(); fence_regs(sx);
    sm_pack<0, 16>(sx, ta);
    issue_s(sx, qb, KD(1));
    sm_mask(ta, mk, false);
    sm_stat(sm_max(ta), m1, true, sta);
    wg_wait<0>(); fence_regs(sx);
    int pr = 0, na = 0;
#pragma unroll 1
    for (int it = 0;; it++) {
      const bool last = pr == 4;
      const int nn = last ? na + 2 : na + 1;
      if (pr == 0) m0 = 0xFF80FF80u;
      if (it == 4) WAITKV(6);
      if (!DBG(1)) attn_block(sx, qa, KD(it == 9 ? na : nn), o0, pb, VD(it == 5 ? na - 1 : na), tb, m0, stb, ((pr + 1) >> 1) <= ti, (pr == 0) | last,
                 last, ta, pa, o1, sta, mk, zero, bars);
      if (it == 9) break;
      if (it == 5) {
        RELKV(5);
        finish(o0, 0, 0);
      }
      if (last) m1 = 0xFF80FF80u;
      if (it == 3) { mbar_wait(bars + 8 * B_QKV2, 0); load_q1(qa, 1); }
      WAITKV(nn + 1);
      if (!DBG(1)) attn_block(sx, qb, KD(nn + 1), o1, pa, VD(na), ta, m1, sta, last || ((pr + 1) >> 1) <= ti, (pr == 3) | last,
                 !last, tb, pb, o0, stb, mk, zero, bars);
      RELKV(na);
      if (it == 3) load_q1(qb, 0);
      if (last) finish(o1, 0, 1);
      na = nn;
      pr = last ? 0 : pr + 1;
    }
    issue_pv(o1, pa, VD(10));
    sm_rescale(o0, stb);
    sm_exp<0, 16>(tb, pb, stb.n0, stb.n1);
    issue_pv(o0, pb, VD(11));
    wg_wait<1>(); fence_regs(o1);
    finish(o1, 1, 1);
    wg_wait<0>(); fence_regs(o0);
    finish(o0, 1, 0);
  } else if (wg == 3) {
    asm volatile("setmaxnreg.dec.sync.aligned.u32 24;");
    if (lane == 0) {
      const uint32_t epoch = read_epoch(), tag = 0x4000u + (epoch & 0x1FFFu);
      if (warp == 12) {
        Ring rg{0, 1};
        const uint32_t ring = sb + SM_RING;
#pragma unroll 1
        for (int k = NSTAGE; k < 7; k++) {
          const uint32_t fb = bars + 8 * (B_FULL + rg.slot);
          mbar_wait(fb + 8 * (B_EMPTY - B_FULL), rg.phase ^ 1);
          tma5d_mc(ring + rg.slot * RING_STAGE + rank * 6144, &tm.qkv, fb, 0, 64 * k + 32 * rank, 0, 0, tj);
          mbar_expect_tx(fb, 12288);
          PROF2(0, k);
          rg.next();
        }
#pragma unroll 1
        for (int k = 0; k < 14; k++) {
          const uint32_t fb = bars + 8 * (B_FULL + rg.slot), dst = ring + rg.slot * RING_STAGE;
          mbar_wait(fb + 8 * (B_EMPTY - B_FULL), rg.phase ^ 1);
          if (rank == 0) tma5d_mc(dst, &tm.qkv, fb, 0, 32 * k, 0, 1, tj);
          else tma3d_mc(dst + 6144, &tm.w1c, fb, 0, 32 * k, 7 * tj);
          mbar_expect_tx(fb, 10240);
          PROF2(0, 7 + k);
          rg.next();
        }
        const CUtensorMap* tma_ = rank ? &tm.w3a : &tm.w1a;
#pragma unroll 1
        for (int k = 0; k < 28; k++) {
          const uint32_t fb = bars + 8 * (B_FULL + rg.slot);
          const int kr = k < 14 ? 32 * k : 32 * (k - 14), at = k < 14 ? 7 * tj + 1 : 7 * tj + 4;
          mbar_wait(fb + 8 * (B_EMPTY - B_FULL), rg.phase ^ 1);
          tma3d_mc(ring + rg.slot * RING_STAGE + rank * 6144, tma_, fb, 0, kr, at);
          mbar_expect_tx(fb, 12288);
          PROF2(0, 21 + k);
          rg.next();
        }
#pragma unroll 1
        for (int k = 0; k < 14; k++) {
          const uint32_t fb = bars + 8 * (B_FULL + rg.slot), dst = ring + rg.slot * RING_STAGE + rank * 6144;
          mbar_wait(fb + 8 * (B_EMPTY - B_FULL), rg.phase ^ 1);
          if (k < 8) tma2d_mc(dst, &tm.w2_48, fb, 56 * ((tj + 1 + k) & 7), 224 * tj + 128 + 48 * rank);
          else tma3d_mc(dst, &tm.wo, fb, 56 * tj, (k >= 11 ? 24 : 0) + 16 * rank, 3 * (k >= 11 ? k - 11 : k - 8));
          mbar_expect_tx(fb, 12288);
          PROF2(0, 49 + k);
          rg.next();
        }
      } else if (warp == 13) {
        l2_prefetch(w2 + (size_t)blockIdx.x * 12544, 12544);
        l2_prefetch(wo + (size_t)blockIdx.x * 3136, 3136);
        mbar_wait_sleep(bars + 8 * B_QKV, 0);
        mbar_arrive(bars + 8 * (B_KVFULL + 0));
        mbar_arrive(bars + 8 * (B_KVFULL + 1));
#pragma unroll 1
        for (int n = 2; n < 12; n++) {
          const int hh = n >= 6, m = n - 6 * hh, dt = m >> 1, b = n & 3;
          int tsrc = ti - dt;
          if (tsrc < 0) tsrc = ti;
          if (!hh || (m & 1) == 0) {
            if (n == 4) flag_wait(&g_kv_flag[(ti * NJ + tj) * 8 + 2], tag);
            flag_wait(&g_kv_flag[(tsrc * NJ + tj) * 8 + (hh ? 1 : 2 * (m & 1))], tag);
            asm volatile("fence.proxy.async.global;" ::: "memory");
          }
          if (n == 2) PROF(51);
          if (n >= 3) mbar_wait_sleep(bars + 8 * (B_KVEMPTY + b), ((n >> 2) - (b == 3 ? 0 : 1)) & 1);
          mbar_expect_tx(bars + 8 * (B_KVFULL + b), 8192);
          bulk_g2s(sb + SM_KV + b * 8192, g_kv + (size_t)(tsrc * NJ + tj) * 32768 + (hh * 2 + (m & 1)) * 8192, 8192, bars + 8 * (B_KVFULL + b));
        }
        mbar_wait(bars + 8 * B_O1, 0);
        PROF(47);
        tma2d_store(&tm.ost, sb + SM_KV, 32 * tj, SEQ + 128 * ti);
        asm volatile("cp.async.bulk.commit_group;" ::: "memory");
        asm volatile("cp.async.bulk.wait_group 0;" ::: "memory");
        asm volatile("fence.proxy.async.global;" ::: "memory");
        asm volatile("fence.acq_rel.gpu;" ::: "memory");
        st_relaxed(&g_o_flag[ti * 32 + 8 + tj], tag);
        PROF(48);
      } else if (warp == 14) {
        if (rank == 1) {
          Ring rg{1, 1};
#pragma unroll 1
          for (int k = 0; k < 14; k++) {
            const uint32_t fb = bars + 8 * (B_FULL + rg.slot);
            mbar_wait(fb + 8 * (B_EMPTY - B_FULL), rg.phase ^ 1);
            tma3d_mc(sb + SM_RING + rg.slot * RING_STAGE + 8192, &tm.w3c, fb, 0, 32 * k, 7 * tj);
            rg.next();
          }
        }
        if (atomicAdd(&g_done, 1u) == gridDim.x - 1) { g_done = 0; st_relaxed(&g_epoch, epoch >= 0x5FFFu ? 0u : epoch + 1u); }
#pragma unroll 1
        for (int p = 0; p < 8; p++) {
          mbar_wait_sleep(bars + 8 * (B_XDEAD + p), 0);
          tma2d_mc(sb + SM_XN + (p < 7 ? p : 0) * 16384 + rank * 8192, &tm.w2_64, bars + 8 * (B_XFULL + p), 56 * ((tj + 1 + p) & 7), 224 * tj + 64 * rank);
          mbar_expect_tx(bars + 8 * (B_XFULL + p), 16384);
        }
      } else {
        mbar_wait_sleep(bars + 8 * B_QKV, 0);
#pragma unroll 1
        for (int hf = 0; hf < 2; hf++) {
          asm volatile("cp.async.bulk.global.shared::cta.bulk_group [%0], [%1], %2;" :: "l"(g_kv + (size_t)(ti * NJ + tj) * 32768 + hf * 8192), "r"(sb + SM_KV + hf * 8192), "r"(8192u) : "memory");
          asm volatile("cp.async.bulk.commit_group;" ::: "memory");
          asm volatile("cp.async.bulk.wait_group 0;" ::: "memory");
          asm volatile("fence.proxy.async.global;" ::: "memory");
          asm volatile("fence.acq_rel.gpu;" ::: "memory");
          st_relaxed(&g_kv_flag[(ti * NJ + tj) * 8 + 2 * hf], tag);
          if (hf == 0) PROF(50);
        }
        mbar_wait_sleep(bars + 8 * B_QKV2, 0);
        asm volatile("fence.acq_rel.gpu;" ::: "memory");
        asm volatile("fence.proxy.async.global;" ::: "memory");
        st_relaxed(&g_kv_flag[(ti * NJ + tj) * 8 + 1], tag);
        PROF(53);
        mbar_wait_sleep(bars + 8 * B_O0, 0);
        PROF(40);
        tma2d_store(&tm.ost, sb + SM_STG, 32 * tj, 128 * ti);
        asm volatile("cp.async.bulk.commit_group;" ::: "memory");
        asm volatile("cp.async.bulk.wait_group 0;" ::: "memory");
        asm volatile("fence.proxy.async.global;" ::: "memory");
        asm volatile("fence.acq_rel.gpu;" ::: "memory");
        st_relaxed(&g_o_flag[ti * 32 + tj], tag);
        {
          unsigned it = 0;
          while (++it < SPIN_LIMIT) {
            const uint4 f0 = ld_b128(&g_o_flag[ti * 32]), f1 = ld_b128(&g_o_flag[ti * 32 + 4]);
            if (((f0.x ^ tag) | (f0.y ^ tag) | (f0.z ^ tag) | (f0.w ^ tag) | (f1.x ^ tag) | (f1.y ^ tag) | (f1.z ^ tag) | (f1.w ^ tag)) == 0) break;
          }
        }
        asm volatile("fence.proxy.async.global;" ::: "memory");
#pragma unroll 1
        for (int kb = 0; kb < 4; kb++) {
          mbar_wait_sleep(bars + 8 * (B_XCONS + kb + 1), 0);
          mbar_expect_tx(bars + 8 * B_OE, 16384);
          tma2d(sb + SM_XN + (kb + 1) * 16384, &tm.o, bars + 8 * B_OE, 64 * kb, 128 * ti);
        }
        mbar_wait_sleep(bars + 8 * (B_XCONS + 5), 0);
        mbar_wait_sleep(bars + 8 * (B_XCONS + 6), 0);
        unsigned todo = 0xF, it = 0;
        while (todo && ++it < SPIN_LIMIT) {
          const uint4 f0 = ld_b128(&g_o_flag[ti * 32 + 8]), f1 = ld_b128(&g_o_flag[ti * 32 + 12]);
          const unsigned own = ld_relaxed(&g_o_flag[ti * 32 + 8 + tj]);
          unsigned rdy = (((f0.x ^ tag) | (f0.y ^ tag)) == 0 ? 1u : 0u) | (((f0.z ^ tag) | (f0.w ^ tag)) == 0 ? 2u : 0u) |
                         (((f1.x ^ tag) | (f1.y ^ tag)) == 0 ? 4u : 0u) | (((f1.z ^ tag) | (f1.w ^ tag) | (own ^ tag)) == 0 ? 8u : 0u);
          rdy &= todo;
          if (rdy) asm volatile("fence.proxy.async.global;" ::: "memory");
#pragma unroll 1
          for (int kb = 0; kb < 4; kb++) {
            if (!((rdy >> kb) & 1u)) continue;
            if (kb == 2) {
              uint32_t done;
              asm volatile("{\n.reg .pred p;\nmbarrier.test_wait.parity.shared::cta.b64 p, [%1], 0;\nselp.u32 %0, 1, 0, p;\n}\n" : "=r"(done) : "r"(bars + 8 * B_XCONS) : "memory");
              if (!done) continue;
            }
            mbar_expect_tx(bars + 8 * (B_OFULL + 1 + kb), 16384);
            tma2d(kb < 2 ? sb + SM_XN + (5 + kb) * 16384 : kb == 2 ? sb + SM_XN : sb + SM_KV + 16384, &tm.o, bars + 8 * (B_OFULL + 1 + kb), 64 * kb, SEQ + 128 * ti);
            todo &= ~(1u << kb);
          }
        }
        PROF(52);
      }
    }
  } else {
    const int w4 = warp & 3, g = lane >> 2, q = lane & 3;
    const int t128 = tid & 127;
    Ring rg{0, 0};
    const uint64_t descA0 = make_desc(sb + SM_XN + wg * 8192, 16, 1024, 1);
    const uint64_t descB64 = make_desc(sb + SM_RING, 2048, 512, 2);
    const uint64_t descB128 = make_desc(sb + SM_RING, 16, 1024, 1);
    const uint64_t descX128 = make_desc(sb + SM_XN, 16, 1024, 1);
    uint32_t h[56];
    const int rloc = 16 * w4 + (lane & 15);
    const uint32_t sw = (rloc >> 1) & 3, chb = lane >> 4;
    {
      float acc[48];
      mbar_wait(bars + 8 * (B_LN + wg), 0);
      GP(0);
      gemm_pass_96(acc, descA0, descB64, bars, rg, lane);
      GP(1);
#pragma unroll
      for (int a = 0; a < 3; a++) {
        const uint32_t base = sb + SM_KV + (1 - wg) * 8192 + (a - 1) * 4096 + rloc * 64;
        uint32_t r[8];
#pragma unroll
        for (int k = 0; k < 8; k++) r[k] = pack_bf16(acc[16 * a + 2 * k], acc[16 * a + 2 * k + 1]);
        if (a == 0 && q >= 2) { r[6] = 0; r[7] = 0; }
        if (a == 2 && q == 2) { r[6] = 0x00003F80u; r[7] = 0x00003F80u; }
        if (a == 0) {
          const uint32_t qs = sb + SM_KV + 3 * 8192 + wg * 4096 + t128 * 16;
          sts128(qs, r[0], r[1], r[2], r[3]); sts128(qs + 2048, r[4], r[5], r[6], r[7]);
        } else {
          stsm_x4(base + (((0 + chb) ^ sw) << 4), r[0], r[1], r[2], r[3]);
          stsm_x4(base + (((2 + chb) ^ sw) << 4), r[4], r[5], r[6], r[7]);
        }
      }
      fence_proxy_async_smem();
      __syncwarp();
      if (lane == 0) mbar_arrive(bars + 8 * B_QKV);
    }
    asm volatile("setmaxnreg.inc.sync.aligned.u32 160;");
    {
      float acc[80];
      GP(13);
      gemm_pass<160, false>(acc, descA0, descB64, bars, rg, lane);
      GP(14);
      uint32_t r[8];
#pragma unroll
      for (int k = 0; k < 8; k++) r[k] = pack_bf16(acc[2 * k], acc[2 * k + 1]);
      if (q < 2) { r[0] = 0; r[1] = 0; }
      uint4* qg = reinterpret_cast<uint4*>(g_q + (size_t)(ti * NJ + tj) * 8192 + wg * 4096) + t128;
      qg[0] = make_uint4(r[0], r[1], r[2], r[3]); qg[128] = make_uint4(r[4], r[5], r[6], r[7]);
      uint4* kvg = reinterpret_cast<uint4*>(g_kv + (size_t)(ti * NJ + tj) * 32768 + (3 - wg) * 8192 + w4 * 1024) + lane;
      const uint32_t stg = sb + SM_STG + warp * 1024;
#pragma unroll
      for (int a = 1; a < 3; a++) {
#pragma unroll
        for (int k = 0; k < 8; k++) r[k] = pack_bf16(acc[16 * a + 2 * k], acc[16 * a + 2 * k + 1]);
        if (a == 2 && q == 0) { r[0] = 0x00003F80u; r[1] = 0x00003F80u; }
        __syncwarp();
        stsm_x4(stg + (lane & 15) * 64 + (((0 + chb) ^ sw) << 4), r[0], r[1], r[2], r[3]);
        stsm_x4(stg + (lane & 15) * 64 + (((2 + chb) ^ sw) << 4), r[4], r[5], r[6], r[7]);
        __syncwarp();
        uint4 v0, v1;
        lds128(stg + lane * 16, v0.x, v0.y, v0.z, v0.w); lds128(stg + 512 + lane * 16, v1.x, v1.y, v1.z, v1.w);
        kvg[(a - 1) * 256] = v0; kvg[(a - 1) * 256 + 32] = v1;
      }
      __syncwarp();
      if (lane == 0) mbar_arrive(bars + 8 * B_QKV2);
#pragma unroll
      for (int k = 0; k < 8; k++) h[k] = pack_bf16(swiglu(acc[48 + 2 * k], acc[64 + 2 * k]), swiglu(acc[48 + 2 * k + 1], acc[64 + 2 * k + 1]));
    }
    {
      float acc[96];
      GP(2);
      gemm_pass<192, false>(acc, descA0, descB64, bars, rg, lane);
      GP(3);
#pragma unroll
      for (int k = 0; k < 24; k++) h[8 + k] = pack_bf16(swiglu(acc[2 * k], acc[48 + 2 * k]), swiglu(acc[2 * k + 1], acc[48 + 2 * k + 1]));
    }
    {
      float acc[96];
      GP(4);
      gemm_pass<192, true>(acc, descA0, descB64, bars, rg, lane);
      GP(5);
#pragma unroll
      for (int k = 0; k < 24; k++) h[32 + k] = pack_bf16(swiglu(acc[2 * k], acc[48 + 2 * k]), swiglu(acc[2 * k + 1], acc[48 + 2 * k + 1]));
    }
    float f0[28], f1[28];
    GP(6);
    const uint32_t t2 = read_epoch() % 3u + 1u, tb0 = t2 & 1u, tb1 = t2 >> 1;
    auto ring_desc = [&]() { return descB128 + (uint64_t)(rg.slot * (RING_STAGE >> 4)); };
    uint32_t prev = 0;
    auto down_pass = [&](float (&f)[28], float (&fo)[28], int p) {
      auto mma = [&](auto kc, uint64_t dB) {
        constexpr int K = decltype(kc)::value;
        wgmma_rs_n56_tb(f, h[4 * K], h[4 * K + 1], h[4 * K + 2], h[4 * K + 3], dB, K > 0);
      };
      uint8_t* dst = g_part + (size_t)(((ti * NJ + ((tj + p) & 7)) * NJ + tj) * 2 + wg) * PART_BYTES;
      auto st = [&](int k) {
        if (p == 0 || DBG(4)) return;
        const uint32_t r0 = (pack_bf16(fo[8 * k], fo[8 * k + 1]) & ~1u) | tb0, r1 = (pack_bf16(fo[8 * k + 2], fo[8 * k + 3]) & ~1u) | tb1;
        if (k < 3) st_b128(dst + k * 2048 + t128 * 16, r0, r1, pack_bf16(fo[k < 3 ? 8 * k + 4 : 0], fo[k < 3 ? 8 * k + 5 : 0]), pack_bf16(fo[k < 3 ? 8 * k + 6 : 0], fo[k < 3 ? 8 * k + 7 : 0]));
        else st_b64(dst + 6144 + t128 * 8, r0, r1);
      };
      const uint64_t dX = descX128 + (uint64_t)((p < 7 ? p : 0) * 1024), dR = ring_desc();
      wg_fence();
      mma(IC<0>{}, dX); mma(IC<1>{}, dX + 128);
      wg_commit();
      if (p > 0) { wg_wait<1>(); arrive_pair(bars + 8 * (B_EMPTY + prev), lane); fence_regs(fo); }
      mma(IC<2>{}, dX + 256); mma(IC<3>{}, dX + 384);
      st(0);
      mma(IC<4>{}, dX + 512); mma(IC<5>{}, dX + 640);
      st(1);
      mma(IC<6>{}, dX + 768); mma(IC<7>{}, dX + 896);
      wg_commit();
      mbar_wait(bars + 8 * (B_FULL + rg.slot), rg.phase);
      mma(IC<8>{}, dR); mma(IC<9>{}, dR + 128);
      st(2);
      mma(IC<10>{}, dR + 256); mma(IC<11>{}, dR + 384);
      st(3);
      if (p < 7) mbar_wait(bars + 8 * (B_XFULL + p + 1), 0);
      mma(IC<12>{}, dR + 512); mma(IC<13>{}, dR + 640);
      wg_commit();
      prev = rg.slot;
      rg.next();
      wg_wait<1>();
      if (p == 0) arrive_pair(bars + 8 * (B_XDEAD + 7), lane);
      else if (lane == 0) mbar_arrive(bars + 8 * (B_XCONS + (p < 7 ? p : 0)));
    };
    mbar_wait(bars + 8 * (B_XFULL + 0), 0);
#pragma unroll
    for (int pp = 0; pp < 4; pp++) { down_pass(f0, f1, 2 * pp); down_pass(f1, f0, 2 * pp + 1); }
    const __nv_bfloat16* xb = x + (size_t)(ti * 128 + wg * 64 + 16 * w4 + g) * DM + tj * 56 + 2 * q;
    uint32_t xr[14], gv[14];
    uint32_t v[4][14];
    auto part_load = [&](int bt) {
#pragma unroll
      for (int u = 0; u < 4; u++) {
        if (u < 4 - bt) {
          const uint8_t* sp = g_part + (size_t)(((ti * NJ + tj) * NJ + ((tj - 1 - 4 * bt - u) & 7)) * 2 + wg) * PART_BYTES;
#pragma unroll
          for (int k = 0; k < 3; k++) { const uint4 w = ld_b128(sp + k * 2048 + t128 * 16); v[u][4 * k] = w.x; v[u][4 * k + 1] = w.y; v[u][4 * k + 2] = w.z; v[u][4 * k + 3] = w.w; }
          const uint2 w = ld_b64(sp + 6144 + t128 * 8); v[u][12] = w.x; v[u][13] = w.y;
        }
      }
    };
    auto part_add = [&](int bt) {
      unsigned it = 0;
      while (true) {
        uint32_t bad = 0;
#pragma unroll
        for (int u = 0; u < 4; u++) {
          if (u < 4 - bt) {
#pragma unroll
            for (int k = 0; k < 4; k++) bad |= (v[u][4 * k] ^ tb0) | (v[u][4 * k + 1] ^ tb1);
          }
        }
        if (!(bad & 1u) || ++it >= SPIN_LIMIT || DBG(4 | 8)) break;
        part_load(bt);
      }
#pragma unroll
      for (int u = 0; u < 4; u++) {
        if (u < 4 - bt) {
#pragma unroll
          for (int k = 0; k < 14; k++) { f1[2 * k] += bf_lo(v[u][k]); f1[2 * k + 1] += bf_hi(v[u][k]); }
        }
      }
      __syncwarp();
    };
    auto wo_half = [&](int bt) {
#pragma unroll
      for (int st = 0; st < 3; st++) {
        mbar_wait(bars + 8 * (B_FULL + rg.slot), rg.phase);
        if (bt == 0) { if (st == 0) mbar_wait(bars + 8 * B_OE, 0); }
        else { if (st == 0) mbar_wait(bars + 8 * (B_OFULL + 1), 0); mbar_wait(bars + 8 * (B_OFULL + 2 + st), 0); if (st == 0) GP(8); }
        const uint64_t dB = ring_desc();
        wg_fence();
#pragma unroll
        for (int u = 0; u < (st < 2 ? 6 : 4); u++) {
          const int hd = 3 * st + (u >> 1);
          const uint32_t xo = bt == 0 ? ((hd >> 1) + 1) * 16384 : hd < 4 ? (5 + (hd >> 1)) * 16384 : hd < 6 ? 0 : SM_KV + 16384;
          const uint64_t dA = descA0 + (uint64_t)(xo >> 4) + (hd & 1) * 4 + (u & 1) * 2;
          wgmma_ss_n56_tb(f0, dA, dB + (u & 1) * 384 + (u >> 1) * 128, bt > 0 || st > 0 || u > 0);
        }
        wg_commit();
        rg.next();
      }
    };
    GP(7);
    wg_wait<0>(); arrive_pair(bars + 8 * (B_EMPTY + prev), lane); fence_regs(f1);
    if (!DBG(4 | 8)) part_load(0);
    wo_half(0);
#pragma unroll 1
    for (int bt = 0; bt < 2; bt++) {
      part_add(bt);
      if (bt == 0 && !DBG(4 | 8)) part_load(1);
    }
#pragma unroll
    for (int k = 0; k < 14; k++) asm volatile("ld.global.nc.b32 %0, [%1];" : "=r"(xr[k]) : "l"(xb + 8 * (k >> 1) + (k & 1) * 8 * DM) : "memory");
    GP(15);
#pragma unroll
    for (int k = 0; k < 14; k++) {
      const uint32_t fv = pack_bf16(f1[2 * k], f1[2 * k + 1]);
      gv[k] = pack_bf16(swiglu(bf_lo(fv), 1.0f), swiglu(bf_hi(fv), 1.0f));
    }
    fence_u32(gv);
    wo_half(1);
    GP(9);
    wg_wait<0>();
    fence_regs(f0);
    GP(11);
    uint32_t ov[16];
#pragma unroll
    for (int k = 0; k < 14; k++) ov[k] = bf2_add(xr[k], bf2_mul(pack_bf16(f0[2 * k], f0[2 * k + 1]), gv[k]));
    ov[14] = ov[12]; ov[15] = ov[13];
    const uint32_t ost = sb + SM_KV + warp * 1792, orow = ost + (lane & 15) * 112;
#pragma unroll
    for (int k = 0; k < 4; k++) stsm_x4(orow + 32 * k + (k < 3 ? 16 * chb : 0), ov[4 * k], ov[4 * k + 1], ov[4 * k + 2], ov[4 * k + 3]);
    fence_proxy_async_smem();
    __syncwarp();
    if (lane == 0) {
      tma2d_store(&tm.out, ost, 56 * tj, 128 * ti + 16 * warp);
      asm volatile("cp.async.bulk.commit_group;" ::: "memory");
      asm volatile("cp.async.bulk.wait_group.read 0;" ::: "memory");
    }
    GP(12);
  }
}

typedef CUresult (*EncodeFn)(CUtensorMap*, CUtensorMapDataType, cuuint32_t, void*, const cuuint64_t*, const cuuint64_t*, const cuuint32_t*,
                             const cuuint32_t*, CUtensorMapInterleave, CUtensorMapSwizzle, CUtensorMapL2promotion, CUtensorMapFloatOOBfill);

bool encode(EncodeFn fn, CUtensorMap* m, const void* base, int rank, const cuuint64_t* dims, const cuuint64_t* strides, const cuuint32_t* box, CUtensorMapSwizzle sw) {
  cuuint32_t es[5] = {1, 1, 1, 1, 1};
  return fn(m, CU_TENSOR_MAP_DATA_TYPE_BFLOAT16, rank, const_cast<void*>(base), dims, strides, box, es, CU_TENSOR_MAP_INTERLEAVE_NONE, sw,
            CU_TENSOR_MAP_L2_PROMOTION_L2_128B, CU_TENSOR_MAP_FLOAT_OOB_FILL_NONE) == CUDA_SUCCESS;
}

}

extern "C" void kernel_launch(void* const* d_in, const int* in_sizes, int n_in, void* d_out, int out_size) {
  const void* x = d_in[0]; const void* wqkv = d_in[1]; const void* wo = d_in[2];
  const void* w1 = d_in[4]; const void* w3 = d_in[5]; const void* w2 = d_in[6];
  void* fnp = nullptr;
  cudaDriverEntryPointQueryResult qr;
  cudaGetDriverEntryPoint("cuTensorMapEncodeTiled", &fnp, cudaEnableDefault, &qr);
  EncodeFn fn = (EncodeFn)fnp;
  void* o_ptr = nullptr;
  cudaGetSymbolAddress(&o_ptr, g_o);
  TMaps tm;
  bool ok = fn != nullptr;
  if (ok) {
    {
      cuuint64_t dims[5] = {32, 448, 3, 2, 8}; cuuint64_t str[4] = {2688, 896, 48, 112}; cuuint32_t box[5] = {32, 32, 3, 1, 1};
      ok &= encode(fn, &tm.qkv, wqkv, 5, dims, str, box, CU_TENSOR_MAP_SWIZZLE_64B);
    }
    {
      cuuint64_t dims[3] = {32, 448, 56}; cuuint64_t str[2] = {3584, 64}; cuuint32_t boxa[3] = {32, 32, 3}, boxc[3] = {32, 32, 1};
      ok &= encode(fn, &tm.w1a, w1, 3, dims, str, boxa, CU_TENSOR_MAP_SWIZZLE_64B);
      ok &= encode(fn, &tm.w3a, w3, 3, dims, str, boxa, CU_TENSOR_MAP_SWIZZLE_64B);
      ok &= encode(fn, &tm.w1c, w1, 3, dims, str, boxc, CU_TENSOR_MAP_SWIZZLE_64B);
      ok &= encode(fn, &tm.w3c, w3, 3, dims, str, boxc, CU_TENSOR_MAP_SWIZZLE_64B);
    }
    {
      cuuint64_t dims[2] = {448, 1792}, dimx[2] = {448, 2048}; cuuint64_t str[1] = {896};
      cuuint32_t b64[2] = {64, 64}, b48[2] = {64, 48}, boxo[2] = {64, 128}, boxs[2] = {32, 128}, boxx[2] = {64, 32};
      ok &= encode(fn, &tm.w2_64, w2, 2, dims, str, b64, CU_TENSOR_MAP_SWIZZLE_128B);
      ok &= encode(fn, &tm.w2_48, w2, 2, dims, str, b48, CU_TENSOR_MAP_SWIZZLE_128B);
      cuuint64_t dimo[3] = {448, 56, 8}, stro[2] = {896, 56 * 896}; cuuint32_t boxwo[3] = {64, 16, 3};
      ok &= encode(fn, &tm.wo, wo, 3, dimo, stro, boxwo, CU_TENSOR_MAP_SWIZZLE_128B);
      cuuint64_t dimp[2] = {256, 4096}; cuuint64_t strp[1] = {512};
      ok &= encode(fn, &tm.o, o_ptr, 2, dimp, strp, boxo, CU_TENSOR_MAP_SWIZZLE_128B);
      ok &= encode(fn, &tm.ost, o_ptr, 2, dimp, strp, boxs, CU_TENSOR_MAP_SWIZZLE_64B);
      ok &= encode(fn, &tm.x, x, 2, dimx, str, boxx, CU_TENSOR_MAP_SWIZZLE_128B);
      cuuint32_t boxw[2] = {56, 16};
      ok &= encode(fn, &tm.out, d_out, 2, dimx, str, boxw, CU_TENSOR_MAP_SWIZZLE_NONE);
    }
  }
  if (!ok) { fprintf(stderr, "tensor map encode failed\n"); return; }
  cudaFuncSetAttribute(fused_kernel, cudaFuncAttributeMaxDynamicSharedMemorySize, SM_TOTAL);
  fused_kernel<<<128, 512, SM_TOTAL, cudaStreamPerThread>>>(tm,
      (const __nv_bfloat16*)x, (const uint8_t*)wqkv, (const uint8_t*)wo, (const uint8_t*)w1, (const uint8_t*)w3, (const uint8_t*)w2,
      (__nv_bfloat16*)d_out, 0);
}
```
